```python
import torch

def _softmax(x, axis=-1):
    return torch.softmax(x, dim=axis)

def _gelu(x):
    return torch.nn.functional.gelu(x, approximate='tanh')

def _silu(x):
    return torch.nn.functional.silu(x)

def _sigmoid(x):
    return torch.sigmoid(x)

def _layernorm(x, axis=-1, eps=1e-05):
    m = x.mean(dim=axis, keepdim=True)
    v = x.var(dim=axis, keepdim=True, unbiased=False)
    return (x - m) / torch.sqrt(v + eps)

def _scatter_add(tgt, idx, src, axis=0):
    return tgt.clone().index_add_(axis, idx, src)

def _segment_sum(src, seg, n):
    out = torch.zeros((n,) + src.shape[1:], dtype=src.dtype)
    return out.index_add_(0, seg, src)

def _pad(x, pw):
    flat = tuple((v for pair in reversed(pw) for v in pair))
    return torch.nn.functional.pad(x, flat)
kernel_name = 'concat_heads__ssm_conv_s4__memory_aug_recurrent_mem_tr__prompt'

def setup_inputs():

    _w = lambda a: (lambda t: t.to(torch.bfloat16) if t.is_floating_point() else t)(torch.as_tensor(a))

    def _A_setup():
        B, L, D, N = (1, 2048, 512, 128)
        A_re = -(lambda _x: torch.exp(torch.as_tensor(_x)))((lambda *s: torch.randn(*s, dtype=torch.bfloat16) * 3.2)(D, N))
        A_im = torch.pi * (lambda *s: torch.randn(*s, dtype=torch.bfloat16) * 0.05)(D, N)
        B_re = (lambda *s: torch.randn(*s, dtype=torch.bfloat16) * 0.2)(D, N)
        B_im = (lambda *s: torch.randn(*s, dtype=torch.bfloat16) * 0.2)(D, N)
        C_re = (lambda *s: torch.randn(*s, dtype=torch.bfloat16) * 0.2)(D, N)
        C_im = (lambda *s: torch.randn(*s, dtype=torch.bfloat16) * 0.2)(D, N)
        log_dt = (lambda *s: torch.randn(*s, dtype=torch.bfloat16) * 0.05)(D) * 0.5 - 4.0
        Dskip = (lambda *s: torch.randn(*s, dtype=torch.bfloat16) * 0.05)(D)
        return {'u': _w((lambda *s: torch.randn(*s, dtype=torch.bfloat16) * 0.05)(B, L, D)), 'A_re': _w(A_re), 'A_im': _w(A_im), 'B_re': _w(B_re), 'B_im': _w(B_im), 'C_re': _w(C_re), 'C_im': _w(C_im), 'log_dt': _w(log_dt), 'Dskip': _w(Dskip)}
    _A_in = _A_setup()

    def _B_setup():
        B, S, Dm = (1, 2048, 512)
        H, Dh = (32, 128)
        M, seg = (8, 32)
        seg = min(seg, S)
        S = S // seg * seg
        return {'x': _w((lambda *s: torch.randn(*s, dtype=torch.bfloat16) * 0.05)(B, S, Dm)), 'mem0': _w((lambda *s: torch.randn(*s, dtype=torch.bfloat16) * 0.4)(B, M, Dm)), 'Wq': _w((lambda *s: torch.randn(*s, dtype=torch.bfloat16) * 6.4)(Dm, H, Dh) * Dm ** (-0.5)), 'Wk': _w((lambda *s: torch.randn(*s, dtype=torch.bfloat16) * 6.4)(Dm, H, Dh) * Dm ** (-0.5)), 'Wv': _w((lambda *s: torch.randn(*s, dtype=torch.bfloat16) * 0.4)(Dm, H, Dh) * Dm ** (-0.5)), 'Wo': _w((lambda *s: torch.randn(*s, dtype=torch.bfloat16) * 0.4)(H, Dh, Dm) * (H * Dh) ** (-0.5)), 'seg_len': seg}
    _B_in = _B_setup()
    return {'A_u': _A_in['u'], 'A_A_re': _A_in['A_re'], 'A_A_im': _A_in['A_im'], 'A_B_re': _A_in['B_re'], 'A_B_im': _A_in['B_im'], 'A_C_re': _A_in['C_re'], 'A_C_im': _A_in['C_im'], 'A_log_dt': _A_in['log_dt'], 'A_Dskip': _A_in['Dskip'], 'B_x': _B_in['x'], 'B_mem0': _B_in['mem0'], 'B_Wq': _B_in['Wq'], 'B_Wk': _B_in['Wk'], 'B_Wv': _B_in['Wv'], 'B_Wo': _B_in['Wo'], 'B_seg_len': _B_in['seg_len']}

def reference(A_u, A_A_re, A_A_im, A_B_re, A_B_im, A_C_re, A_C_im, A_log_dt, A_Dskip, B_x, B_mem0, B_Wq, B_Wk, B_Wv, B_Wo, B_seg_len):

    def _A_ref(u, A_re, A_im, B_re, B_im, C_re, C_im, log_dt, Dskip):
        Bsz, L, D = u.shape
        dt = torch.exp(log_dt)[:, None]
        A = A_re + 1j * A_im
        Bc = B_re + 1j * B_im
        Cc = C_re + 1j * C_im
        logdA = dt * A
        dB = dt * Bc
        l = (lambda x, dt: x.to(dt))(torch.arange(L), A_re.dtype)
        P = torch.exp(logdA[:, :, None] * l[None, None, :])
        K = torch.einsum('dn,dnl,dn->dl', Cc, P, dB).real
        L2 = 2 * L
        Kp = _pad(K, ((0, 0), (0, L)))
        up = (lambda x, *d: x.permute(*d))(u, 0, 2, 1)
        up = _pad(up, ((0, 0), (0, 0), (0, L)))
        Kf = (lambda x, axes=(-2, -1): torch.fft.rfft2(x.float(), dim=axes))(Kp[:, None, :], axes=(-2, -1))
        Uf = (lambda x, axes=(-2, -1): torch.fft.rfft2(x.float(), dim=axes))(up[:, :, None, :], axes=(-2, -1))
        Yf = Uf * Kf[None, :, :, :]
        y = (lambda x, s, axes=(-2, -1): torch.fft.irfft2(x, s=s, dim=axes).to(torch.bfloat16))(Yf, (1, L2), axes=(-2, -1))[:, :, 0, :L]
        y = (lambda x, *d: x.permute(*d))(y, 0, 2, 1) + u * Dskip[None, None, :]
        return y

    def _B_ref(x, mem0, Wq, Wk, Wv, Wo, seg_len):
        B, S, Dm = x.shape
        H, Dh = (Wq.shape[1], Wq.shape[2])
        M = mem0.shape[1]
        scale = Dh ** (-0.5)
        n_seg = S // seg_len
        L = M + seg_len
        idx = torch.arange(L)
        mask = (idx[:, None] < M) | (idx[:, None] >= idx[None, :])
        mem = mem0
        outs = []
        for s in range(n_seg):
            xs = x[:, s * seg_len:(s + 1) * seg_len, :].clone()
            h = torch.concatenate([mem, xs], axis=1)
            q = torch.einsum('btd,dhe->bhte', h, Wq)
            k = torch.einsum('btd,dhe->bhte', h, Wk)
            v = torch.einsum('btd,dhe->bhte', h, Wv)
            scores = torch.einsum('bhqe,bhke->bhqk', q, k) * scale
            scores = torch.where(mask[None, None], scores, -1000000000.0)
            p = _softmax(scores, axis=-1)
            o = torch.einsum('bhqk,bhke->bhqe', p, v)
            o = torch.einsum('bhte,hed->btd', o, Wo)
            mem = o[:, :M, :].clone()
            outs.append(o[:, M:, :])
        return torch.concatenate(outs, axis=1)
    a = _A_ref(A_u, A_A_re, A_A_im, A_B_re, A_B_im, A_C_re, A_C_im, A_log_dt, A_Dskip)
    b = _B_ref(B_x, B_mem0, B_Wq, B_Wk, B_Wv, B_Wo, B_seg_len)
    return torch.concatenate([a, b], axis=-1)
```

```cpp
#include <cuda_runtime.h>
#include <cuda_bf16.h>
#include <cuda.h>
#include <stdint.h>

typedef __nv_bfloat16 bf16;
namespace {
constexpr int LTOK=2048, DM=512, NH=32, HE=128, NMEM=8, SEG=32, NSEG=64;

__device__ __align__(1024) unsigned long long g_acc[4*4096];
__device__ __align__(128) bf16 g_qx[NH*NSEG*HE*SEG];
__device__ __align__(128) bf16 g_kx[NH*NSEG*HE*SEG];
__device__ __align__(128) bf16 g_vx[NH*NSEG*HE*SEG];
__device__ __align__(128) bf16 g_km[NH*NSEG*HE*NMEM];
__device__ __align__(128) bf16 g_vm[NH*NSEG*HE*NMEM];
__device__ __align__(128) bf16 g_o[LTOK*NH*HE];
struct Ctrl { unsigned start_cnt; unsigned pad0[31]; unsigned bar_cnt; unsigned pad1[31]; unsigned err; unsigned pad2[31];
              unsigned xmax[2]; unsigned nv[2]; unsigned pad3[28]; unsigned noh[2][32];
              unsigned rpub; unsigned pad4[31];
              unsigned segflag[NSEG*8];
              unsigned oflag[NSEG*8];
              unsigned pcnt[NSEG*8];
              unsigned fcnt[NSEG*8]; };
__device__ Ctrl g_ctrl;
#define STAMP(i)
#define TL(i)
#define TLSETUP
#define SCHED_FENCE() __syncwarp()
__device__ __forceinline__ uint32_t smem_u32(const void* p){ return (uint32_t)__cvta_generic_to_shared(p);}
__device__ __forceinline__ uint32_t mapa(uint32_t a, uint32_t r){ uint32_t o; asm volatile("mapa.shared::cluster.u32 %0,%1,%2;":"=r"(o):"r"(a),"r"(r)); return o;}
__device__ __forceinline__ void mbar_init(uint32_t a, uint32_t c){ asm volatile("mbarrier.init.shared::cta.b64 [%0],%1;"::"r"(a),"r"(c):"memory");}
__device__ __forceinline__ void mbar_expect_tx(uint32_t a, uint32_t b){ asm volatile("mbarrier.arrive.expect_tx.shared::cta.b64 _,[%0],%1;"::"r"(a),"r"(b):"memory");}
__device__ __forceinline__ void mbar_arrive(uint32_t a){ asm volatile("mbarrier.arrive.shared::cta.b64 _,[%0];"::"r"(a):"memory");}
__device__ __forceinline__ bool mbar_try(uint32_t a, uint32_t ph){ uint32_t ok; asm volatile("{.reg .pred p; mbarrier.try_wait.parity.shared::cta.b64 p,[%1],%2; selp.u32 %0,1,0,p;}":"=r"(ok):"r"(a),"r"(ph):"memory"); return ok;}
__device__ __forceinline__ bool mbar_test(uint32_t a, uint32_t ph){ uint32_t ok; asm volatile("{.reg .pred p; mbarrier.test_wait.parity.shared::cta.b64 p,[%1],%2; selp.u32 %0,1,0,p;}":"=r"(ok):"r"(a),"r"(ph):"memory"); return ok;}
__device__ __forceinline__ void mbar_wait(uint32_t a,uint32_t ph){ int c=0; while(!mbar_try(a,ph)){ if(++c>(1<<22)){ g_ctrl.err=1; break; } } }
__device__ __forceinline__ void st_async1(uint32_t dst, uint32_t v, uint32_t mbar){ asm volatile("st.async.weak.shared::cluster.mbarrier::complete_tx::bytes.b32 [%0],%1,[%2];"::"r"(dst),"r"(v),"r"(mbar):"memory");}

__device__ __forceinline__ void cp16(uint32_t dst,const void* src){ asm volatile("cp.async.cg.shared.global [%0],[%1],16;"::"r"(dst),"l"(src):"memory");}
__device__ __forceinline__ void ldsm4(uint32_t* r,uint32_t a){ asm volatile("ldmatrix.sync.aligned.m8n8.x4.shared.b16 {%0,%1,%2,%3},[%4];":"=r"(r[0]),"=r"(r[1]),"=r"(r[2]),"=r"(r[3]):"r"(a):"memory");}
__device__ __forceinline__ void ldsm4t(uint32_t* r,uint32_t a){ asm volatile("ldmatrix.sync.aligned.m8n8.x4.trans.shared.b16 {%0,%1,%2,%3},[%4];":"=r"(r[0]),"=r"(r[1]),"=r"(r[2]),"=r"(r[3]):"r"(a):"memory");}
__device__ __forceinline__ void mma_bf16(float* d,uint32_t a0,uint32_t a1,uint32_t a2,uint32_t a3,uint32_t b0,uint32_t b1){
  asm volatile("mma.sync.aligned.m16n8k16.row.col.f32.bf16.bf16.f32 {%0,%1,%2,%3},{%4,%5,%6,%7},{%8,%9},{%0,%1,%2,%3};":"+f"(d[0]),"+f"(d[1]),"+f"(d[2]),"+f"(d[3]):"r"(a0),"r"(a1),"r"(a2),"r"(a3),"r"(b0),"r"(b1)); }
__device__ __forceinline__ uint32_t movm_t(uint32_t a){ uint32_t d; asm volatile("movmatrix.sync.aligned.m8n8.trans.b16 %0,%1;":"=r"(d):"r"(a)); return d;}
__device__ __forceinline__ uint32_t pack_bf16(float lo,float hi){ uint32_t r; asm("cvt.rn.bf16x2.f32 %0,%1,%2;":"=r"(r):"f"(hi),"f"(lo)); return r;}
__device__ __forceinline__ void bar_sync(int id,int n){ asm volatile("bar.sync %0,%1;"::"r"(id),"r"(n):"memory");}
__device__ __forceinline__ void bar_arrive(int id,int n){ asm volatile("bar.arrive %0,%1;"::"r"(id),"r"(n):"memory");}
__device__ __forceinline__ uint4 ld_relaxed_v4(const void* p){ uint4 v; asm volatile("ld.relaxed.gpu.global.v4.u32 {%0,%1,%2,%3},[%4];":"=r"(v.x),"=r"(v.y),"=r"(v.z),"=r"(v.w):"l"(p):"memory"); return v;}
__device__ __forceinline__ unsigned ld_relaxed_u32(const void* p){ unsigned v; asm volatile("ld.relaxed.gpu.global.u32 %0,[%1];":"=r"(v):"l"(p):"memory"); return v;}
__device__ __forceinline__ void red_u64(void* p, uint32_t lo,uint32_t hi){ asm volatile("{.reg .b64 v; mov.b64 v,{%1,%2}; red.relaxed.gpu.global.add.u64 [%0],v;}"::"l"(p),"r"(lo),"r"(hi):"memory");}
__device__ __forceinline__ unsigned clk32(){ unsigned t; asm volatile("mov.u32 %0,%%clock;":"=r"(t)::"memory"); return t; }
__device__ __forceinline__ float ex2(float x){ float y; asm("ex2.approx.ftz.f32 %0,%1;":"=f"(y):"f"(x)); return y; }
__device__ __forceinline__ float bf_lo(uint32_t w){ return __uint_as_float(w<<16);}
__device__ __forceinline__ float bf_hi(uint32_t w){ return __uint_as_float(w&0xffff0000u);}
__device__ __forceinline__ uint32_t pin(uint32_t x){ uint32_t y; asm volatile("mov.b32 %0,%1;":"=r"(y):"r"(x)); return y; }
__device__ __forceinline__ int sgxt29(uint32_t x){ int y; asm("bfe.s32 %0,%1,0,29;":"=r"(y):"r"(x)); return y; }
__device__ __forceinline__ uint32_t maxabs_bf2(uint32_t a,uint32_t b){ uint32_t y; asm("max.xorsign.abs.bf16x2 %0,%1,%2;":"=r"(y):"r"(a),"r"(b)); return y; }
__device__ __forceinline__ void backoff(int n){ unsigned t0=clk32(); while((int)(clk32()-t0)<n){} }
__device__ __forceinline__ unsigned gtime32(){ unsigned t; asm volatile("mov.u32 %0,%%globaltimer_lo;":"=r"(t)::"memory"); return t; }
__device__ __forceinline__ void red_max_u32(void* p,unsigned v){ asm volatile("red.relaxed.gpu.global.max.u32 [%0],%1;"::"l"(p),"r"(v):"memory"); }
__device__ __forceinline__ void sts32(uint32_t a,uint32_t v){ asm volatile("st.shared.b32 [%0],%1;"::"r"(a),"r"(v):"memory"); }
__device__ __forceinline__ void sts128f(uint32_t a,float x,float y,float z,float w){ asm volatile("st.shared.v4.f32 [%0],{%1,%2,%3,%4};"::"r"(a),"f"(x),"f"(y),"f"(z),"f"(w):"memory"); }
__device__ __forceinline__ float4 lds128f(uint32_t a){ float4 v; asm volatile("ld.shared.v4.f32 {%0,%1,%2,%3},[%4];":"=f"(v.x),"=f"(v.y),"=f"(v.z),"=f"(v.w):"r"(a):"memory"); return v; }
__device__ __forceinline__ void lds128u(uint32_t* v,uint32_t a){ asm volatile("ld.shared.v4.b32 {%0,%1,%2,%3},[%4];":"=r"(v[0]),"=r"(v[1]),"=r"(v[2]),"=r"(v[3]):"r"(a):"memory"); }
__device__ __forceinline__ void mma_k8(float* d,uint32_t a0,uint32_t a1,uint32_t b0){
  asm volatile("mma.sync.aligned.m16n8k8.row.col.f32.bf16.bf16.f32 {%0,%1,%2,%3},{%4,%5},{%6},{%0,%1,%2,%3};":"+f"(d[0]),"+f"(d[1]),"+f"(d[2]),"+f"(d[3]):"r"(a0),"r"(a1),"r"(b0)); }
__device__ __forceinline__ void tma_x_mc(uint32_t dst,const CUtensorMap* m,int c0,int c1,uint32_t mbar){
  asm volatile("cp.async.bulk.tensor.2d.shared::cluster.global.mbarrier::complete_tx::bytes.multicast::cluster [%0],[%1,{%2,%3}],[%4],%5;"::"r"(dst),"l"(m),"r"(c0),"r"(c1),"r"(mbar),"h"((unsigned short)7):"memory"); }
__device__ __forceinline__ void bulk_s2s(uint32_t dst,uint32_t src,uint32_t bytes,uint32_t mbar){ asm volatile("cp.async.bulk.shared::cluster.shared::cta.mbarrier::complete_tx::bytes [%0],[%1],%2,[%3];"::"r"(dst),"r"(src),"r"(bytes),"r"(mbar):"memory");}
__device__ __forceinline__ void bulk_s2g(void* dst,uint32_t src,uint32_t bytes,int ef=0){
  if(ef){ asm volatile("{ .reg .b64 pol; createpolicy.fractional.L2::evict_first.b64 pol,1.0; cp.async.bulk.global.shared::cta.bulk_group.L2::cache_hint [%0],[%1],%2,pol; }"::"l"(dst),"r"(src),"r"(bytes):"memory"); }
  else asm volatile("cp.async.bulk.global.shared::cta.bulk_group [%0],[%1],%2;"::"l"(dst),"r"(src),"r"(bytes):"memory");
  asm volatile("cp.async.bulk.commit_group;":::"memory"); }
__device__ __forceinline__ void stsm4(uint32_t a,uint32_t r0,uint32_t r1,uint32_t r2,uint32_t r3){ asm volatile("stmatrix.sync.aligned.m8n8.x4.shared.b16 [%0],{%1,%2,%3,%4};"::"r"(a),"r"(r0),"r"(r1),"r"(r2),"r"(r3):"memory"); }
__device__ __forceinline__ void wg_fence(){ asm volatile("wgmma.fence.sync.aligned;":::"memory"); }
__device__ __forceinline__ void wg_commit(){ asm volatile("wgmma.commit_group.sync.aligned;":::"memory"); }
__device__ __forceinline__ void wg_wait0(){ asm volatile("wgmma.wait_group.sync.aligned 0;":::"memory"); }
template<int FIRST,int OFF> __device__ __forceinline__ void wgmma_n32(float* d,const uint32_t* a,uint32_t dlo){
  asm volatile("{ .reg .pred p; .reg .b32 lo; .reg .b64 dd; setp.ne.b32 p,%21,0; add.u32 lo,%20,%22; mov.b64 dd,{lo,0x40000040};\n wgmma.mma_async.sync.aligned.m64n32k16.f32.bf16.bf16 {%0,%1,%2,%3,%4,%5,%6,%7,%8,%9,%10,%11,%12,%13,%14,%15},{%16,%17,%18,%19},dd,p,1,1,0; }"
   :"+f"(d[0]),"+f"(d[1]),"+f"(d[2]),"+f"(d[3]),"+f"(d[4]),"+f"(d[5]),"+f"(d[6]),"+f"(d[7]),"+f"(d[8]),"+f"(d[9]),"+f"(d[10]),"+f"(d[11]),"+f"(d[12]),"+f"(d[13]),"+f"(d[14]),"+f"(d[15])
   :"r"(a[0]),"r"(a[1]),"r"(a[2]),"r"(a[3]),"r"(dlo),"n"(FIRST?0:1),"n"(OFF)); }
template<int K0,int K1> struct ShadowRange { static __device__ __forceinline__ void run(float* d,const uint32_t* w,uint32_t dlo){ wgmma_n32<(K0==0),(((K0>>2)*4096+(K0&3)*32)>>4)>(d,&w[K0*4],dlo); ShadowRange<K0+1,K1>::run(d,w,dlo); } };
template<int K1> struct ShadowRange<K1,K1> { static __device__ __forceinline__ void run(float*,const uint32_t*,uint32_t){} };
__device__ __forceinline__ void put_red(char* ra,const float* x,const float* y){
  const float MG=12582912.f;
  int A=__float_as_int((x[0]+y[0])+MG)-0x4B400000, B=__float_as_int((x[1]+y[1])+MG)-0x4B400000, A2=__float_as_int((x[2]+y[2])+MG)-0x4B400000, B2=__float_as_int((x[3]+y[3])+MG)-0x4B400000;
  red_u64(ra,(uint32_t)(B*64+1),(uint32_t)(A*8+(B>>26))); red_u64(ra+512,(uint32_t)(B2*64+1),(uint32_t)(A2*8+(B2>>26))); }
__host__ __device__ __forceinline__ int tile_off(int e,int tok){ return e*32 + ((((tok>>3)^((e>>1)&3)))<<3) + (tok&7); }

__device__ __forceinline__ void bulk_g2s(uint32_t dst,const void* src,uint32_t bytes,uint32_t mbar){ asm volatile("cp.async.bulk.shared::cta.global.mbarrier::complete_tx::bytes [%0],[%1],%2,[%3];"::"r"(dst),"l"(src),"r"(bytes),"r"(mbar):"memory");}
__device__ __forceinline__ void tma_2d(uint32_t dst,const CUtensorMap* m,int c0,int c1,uint32_t mbar){
  asm volatile("cp.async.bulk.tensor.2d.shared::cta.global.mbarrier::complete_tx::bytes [%0],[%1,{%2,%3}],[%4];"::"r"(dst),"l"(m),"r"(c0),"r"(c1),"r"(mbar):"memory"); }
__device__ __forceinline__ unsigned ld_acquire_u32(const void* p){ unsigned v; asm volatile("ld.acquire.gpu.global.u32 %0,[%1];":"=r"(v):"l"(p):"memory"); return v;}
__device__ __forceinline__ void red_add_u32(void* p,unsigned v){ asm volatile("red.relaxed.gpu.global.add.u32 [%0],%1;"::"l"(p),"r"(v):"memory"); }
__device__ __forceinline__ void atom_max_done(unsigned* p,unsigned v,uint32_t scratch){ asm volatile("{ .reg .u32 o; atom.relaxed.gpu.global.max.u32 o,[%0],%1; st.shared.u32 [%2],o; }"::"l"(p),"r"(v),"r"(scratch):"memory"); }
__device__ __forceinline__ void smem_inc_release(uint32_t a){ asm volatile("red.release.cta.shared::cta.add.u32 [%0],1;"::"r"(a):"memory"); }
__device__ __forceinline__ unsigned smem_ld_acquire(uint32_t a){ unsigned v; asm volatile("ld.acquire.cta.shared::cta.u32 %0,[%1];":"=r"(v):"r"(a):"memory"); return v; }
__device__ __forceinline__ void fence_gpu(){ asm volatile("fence.acq_rel.gpu;":::"memory"); }
__device__ __forceinline__ uint32_t opq(uint32_t v){ asm volatile("":"+r"(v)); return v; }
__device__ __forceinline__ void wait_flags2(const unsigned* p,unsigned tp,const unsigned* q,unsigned tq){ int c=0;
  while(true){ const unsigned b=ld_relaxed_u32(q), a=ld_acquire_u32(p); if((int)(a-tp)>=0 && (int)(b-tq)>=0) break; __nanosleep(80); if(++c>(1<<24)){ g_ctrl.err=21; break; } } }
__device__ __forceinline__ void quiet_gate(unsigned w0,unsigned w1){
  for(int c=0;c<64;c++){
    const unsigned R=ld_relaxed_u32(&g_ctrl.rpub); const int d=(int)(gtime32()-R);
    if(d>6000 || d<-6000) return;
    if(d>=(int)w0 && d<(int)w1) return;
    if(d<(int)w0){ const unsigned T=R+w0; int k=0; while((int)(gtime32()-T)<0 && ++k<4000) __nanosleep(20); return; }
    __nanosleep(150); } }
__device__ __forceinline__ void wait_flag(const unsigned* p,unsigned target){ int c=0; while((int)(ld_acquire_u32(p)-target)<0){ __nanosleep(64); if(++c>(1<<24)){ g_ctrl.err=20; break; } } }
constexpr int SH_N1=20;
constexpr int WPITCH=272;
constexpr int SM_STW=0;
constexpr int SM_KV=0;
constexpr int SM_QST=32768;
constexpr int SM_T5C=49152;
constexpr int SM_STO=65536;
constexpr int SM_X=131072;
constexpr int SM_MEM=196608;
constexpr int SM_QKV=SM_MEM+8192;
constexpr int SM_O=SM_QKV+16384;
constexpr int SM_SX=SM_O+2048;
constexpr int SM_BAR=SM_SX+6144;
constexpr int SM_MISC=SM_BAR+128;
constexpr int SM_TOTAL=SM_MISC+384;

struct ChainP { const bf16* x; const bf16* mem0; const bf16* Wo; int delay; unsigned d0, lam0, fpen; int boff; };

__global__ void __launch_bounds__(384,1) chain_kernel(const ChainP p,const __grid_constant__ CUtensorMap tmx,const __grid_constant__ CUtensorMap tmq,const __grid_constant__ CUtensorMap tmk,const __grid_constant__ CUtensorMap tmv,const __grid_constant__ CUtensorMap tmwo){
  extern __shared__ __align__(1024) unsigned char sm[];
  const uint32_t sb=smem_u32(sm);
  const int tid=threadIdx.x, warp=__shfl_sync(0xffffffffu,tid>>5,0), lane=tid&31, g=lane>>2, t=lane&3;
  uint32_t r; asm volatile("mov.u32 %0, %%cluster_ctarank;":"=r"(r));
  const int h=blockIdx.x/3;
  const uint32_t mbA=sb+SM_BAR, mbKV=sb+SM_BAR+16, mbX=sb+SM_BAR+32, mbW=sb+SM_BAR+48;
  volatile float* misc=(volatile float*)(sm+SM_MISC); volatile unsigned* sch=(volatile unsigned*)(sm+SM_MISC+192);
  if(tid==0&&blockIdx.x==0) STAMP(0);
  if(tid==0){ mbar_init(mbA,9); mbar_init(mbA+8,9); mbar_init(mbKV,1); mbar_init(mbKV+8,1); mbar_init(mbX,1); mbar_init(mbX+8,1); mbar_init(mbW,1); mbar_init(mbW+8,1);
    asm volatile("fence.mbarrier_init.release.cluster;":::"memory");
    const CUtensorMap* tw=(r==0)? &tmq : (r==1)? &tmk : &tmv;
    mbar_expect_tx(mbW,131072);
    for(int j=0;j<4;j++) tma_2d(sb+SM_STW+(j&1)*65536+(j>>1)*32768,tw,h*HE+(j&1)*64,(j>>1)*256,mbW); }
  __syncthreads();
  if(tid==0){
    for(int sg=0;sg<2;sg++){ mbar_expect_tx(mbX+8*sg,32768); for(int j=0;j<8;j++) tma_2d(sb+SM_X+sg*32768+j*4096,&tmx,j*64,sg*32,mbX+8*sg); }
    for(int j=0;j<3;j++) asm volatile("cp.async.bulk.prefetch.tensor.2d.L2.global.tile [%0,{%1,%2}];"::"l"(&tmwo),"r"(176*(int)r+64*j),"r"(h*HE):"memory"); }
  if(tid==32){ unsigned tk=atomicAdd(&g_ctrl.start_cnt,1); ((volatile unsigned*)misc)[9]=(tk/96)&1; ((volatile unsigned*)misc)[12]=(tk/96+1)*96;
    fence_gpu(); asm volatile("griddepcontrol.launch_dependents;":::"memory"); }
  for(int l=blockIdx.x;l<512;l+=96){ if(tid>=64 && tid<80){ uint4* q=(uint4*)((char*)g_acc+(size_t)l*256)+(tid-64); *q=make_uint4(0,0,0,0);} }
  if(tid>=64 && tid<80) fence_gpu();
  __syncwarp();
  const int ntile=(r==2)?10:11;
  auto grid_wait=[&](){
    const unsigned tgt=((volatile unsigned*)misc)[12]; const int par=((volatile unsigned*)misc)[9]; int c=0;
    while((int)(ld_acquire_u32(&g_ctrl.bar_cnt)-tgt)<0){ if(++c>(1<<22)){ g_ctrl.err=2; break; } }
    float v=__uint_as_float(ld_relaxed_u32(&g_ctrl.noh[par][lane])); const float nv=__uint_as_float(ld_relaxed_u32(&g_ctrl.nv[par])), xm=__uint_as_float(ld_relaxed_u32(&g_ctrl.xmax[par]));
    float no=v, nomax=v;
    #pragma unroll
    for(int o=1;o<32;o<<=1){ no+=__shfl_xor_sync(~0u,no,o); nomax=fmaxf(nomax,__shfl_xor_sync(~0u,nomax,o)); }
    if(lane==0){ misc[8]=nv*fmaxf(no*(1.0f/64.0f),nomax); misc[10]=xm; }
    if(blockIdx.x==0){ g_ctrl.noh[par^1][lane]=0; if(lane==0){ g_ctrl.xmax[par^1]=0; g_ctrl.nv[par^1]=0; } } };
  const char* accb=(const char*)g_acc;
  auto cvt_unit=[&](uint4 x,uint32_t dst,uint32_t& mx){
    int B0=sgxt29(__funnelshift_r(x.x,x.y,6)), B1=sgxt29(__funnelshift_r(x.z,x.w,6));
    int A0=((int)x.y>>3)-(B0>>31), A1=((int)x.w>>3)-(B1>>31);
    uint32_t o0=pack_bf16((float)A0,(float)B0), o1=pack_bf16((float)A1,(float)B1);
    mx=maxabs_bf2(mx,o0); mx=maxabs_bf2(mx,o1);
    asm volatile("st.shared.v2.b32 [%0],{%1,%2};"::"r"(dst),"r"(o0),"r"(o1):"memory"); };
  auto bad_unit=[&](uint4 x){ return ((x.x^32u)|(x.z^32u))&63u; };
  if(warp<8){
    asm volatile("setmaxnreg.inc.sync.aligned.u32 176;");
    uint32_t w[128];
    if(tid==0&&blockIdx.x==0) STAMP(20);
    unsigned nvm=0, xm0=0;
    {
      unsigned mx=0; const uint4* xv=(const uint4*)p.x; uint4 v4[6];
      #pragma unroll
      for(int j=0;j<6;j++){ const int i=(j*96+blockIdx.x)*256+tid; v4[j]=(i<131072)? xv[i] : make_uint4(0,0,0,0); }
      #pragma unroll
      for(int j=0;j<6;j++){ const uint4 v=v4[j]; unsigned a=v.x&0x7fff7fffu,b=v.y&0x7fff7fffu,c=v.z&0x7fff7fffu,d=v.w&0x7fff7fffu;
        unsigned m1=max(max(a&0xffff,a>>16),max(b&0xffff,b>>16)), m2=max(max(c&0xffff,c>>16),max(d&0xffff,d>>16)); mx=max(mx,max(m1,m2)); }
      xm0=__reduce_max_sync(~0u,mx); }
    mbar_wait(mbW,0);
    if(tid==0&&blockIdx.x==0) STAMP(21);
    { const int dr=(lane&7)+8*(lane>>4), e0=16*warp+8*((lane>>3)&1);
      const uint32_t a=sb+SM_STW+(e0>>6)*65536+dr*128+((((e0&63)>>3)^(dr&7))<<4);
      #pragma unroll
      for(int ks=0;ks<32;ks++) ldsm4t(&w[ks*4],a+ks*2048);
      if(r==2){ float s0=0,s1=0;
        #pragma unroll
        for(int ks=0;ks<32;ks++){ s0+=fabsf(bf_lo(w[ks*4]))+fabsf(bf_hi(w[ks*4]))+fabsf(bf_lo(w[ks*4+2]))+fabsf(bf_hi(w[ks*4+2])); s1+=fabsf(bf_lo(w[ks*4+1]))+fabsf(bf_hi(w[ks*4+1]))+fabsf(bf_lo(w[ks*4+3]))+fabsf(bf_hi(w[ks*4+3])); }
        s0+=__shfl_xor_sync(~0u,s0,1); s0+=__shfl_xor_sync(~0u,s0,2); s1+=__shfl_xor_sync(~0u,s1,1); s1+=__shfl_xor_sync(~0u,s1,2);
        nvm=__reduce_max_sync(~0u,__float_as_uint(fmaxf(s0,s1))); } }
    asm volatile("{ .reg .pred p; setp.eq.u32 p,%0,0x7fc1dead; @p st.shared.u32 [%1],%0; }"::"r"(w[127]^w[126]),"r"(sb+SM_MISC+252):"memory");
    if(tid==0&&blockIdx.x==0) STAMP(22);
    if(lane==0){ ((volatile unsigned*)misc)[24+warp]=xm0; ((volatile unsigned*)misc)[32+warp]=nvm; }
    bar_sync(10,256);
    bar_arrive(15,384);
    asm volatile("barrier.cluster.arrive.relaxed.aligned;":::"memory");
    const uint32_t p1=(r+1)%3, p2=(r+2)%3;
    const uint32_t dql=pin(sb+SM_QKV+r*2048+(16*warp+g)*16+t*4);
    const uint32_t dq1=pin(mapa(dql,p1)), dq2=pin(mapa(dql,p2));
    const uint32_t dm1=pin(mapa(mbA,p1)), dm2=pin(mapa(mbA,p2));
    const uint32_t ma=pin(sb+SM_MEM+lane*16);
    const uint32_t tile_l=(r==0? sb+SM_QST : r==1? sb+SM_KV : sb+SM_KV+8192);
    const uint32_t tile_stride=(r==0? 8192u:16384u);
    const uint32_t a_st=pin(tile_l+(16*warp+8*((lane>>3)&1)+(lane&7))*64+((((lane>>4))^(((lane&7)>>1)&3))<<4));
    float sa[16];
    auto shadow_issue1=[&](int seg){
      const uint32_t dlo=(((sb+SM_X+(seg&1)*32768)&0x3FFFF)>>4)|(1u<<16);
      wg_fence();
      ShadowRange<0,SH_N1>::run(sa,w,dlo); };
    auto shadow_issue2=[&](int seg){
      const uint32_t dlo=(((sb+SM_X+(seg&1)*32768)&0x3FFFF)>>4)|(1u<<16);
      ShadowRange<SH_N1,32>::run(sa,w,dlo);
      wg_commit(); };
    auto shadow_epi=[&](int seg){
      wg_wait0();
      const uint32_t a=a_st+(seg&1)*tile_stride;
      stsm4(a,pack_bf16(sa[0],sa[1]),pack_bf16(sa[2],sa[3]),pack_bf16(sa[4],sa[5]),pack_bf16(sa[6],sa[7]));
      stsm4(a^32,pack_bf16(sa[8],sa[9]),pack_bf16(sa[10],sa[11]),pack_bf16(sa[12],sa[13]),pack_bf16(sa[14],sa[15]));
      asm volatile("fence.proxy.async.shared::cta;":::"memory"); };
    auto shadow_send=[&](int seg){
      const uint32_t sb2=opq(sb), r2=opq(r);
      const uint32_t src=sb2+(r2==0? SM_QST+(seg&1)*8192 : SM_KV+(r2-1)*8192+(seg&1)*16384), mb=sb2+SM_BAR+16+(seg&1)*8;
      const uint32_t nb=8192u;
      mbar_expect_tx(mb, r2==0? 2*nb:nb);
      if(r2>0){ const uint32_t q1=(r2+1)%3, q2=(r2+2)%3; bulk_s2s(mapa(src,q1),src,nb,mapa(mb,q1)); bulk_s2s(mapa(src,q2),src,nb,mapa(mb,q2)); } };
    auto shadow_export=[&](int seg){ const uint32_t sb2=opq(sb), r2=opq(r), h2=opq(h);
      const uint32_t src=sb2+(r2==0? SM_QST+(seg&1)*8192 : SM_KV+(r2-1)*8192+(seg&1)*16384);
      bulk_s2g((r2==0? g_qx: r2==1? g_kx: g_vx)+((size_t)h2*NSEG+seg)*4096,src,8192,1); };
    auto km_export=[&](int st){ const uint32_t sb2=opq(sb), r2=opq(r), h2=opq(h);
      if(r2>0) bulk_s2g((r2==1? g_km: g_vm)+((size_t)h2*NSEG+st)*1024,sb2+SM_QKV+(st&1)*8192+r2*2048,2048,1); };
    auto x_load=[&](int seg){
      const uint32_t sb2=opq(sb), r2=opq(r);
      const uint32_t mb=sb2+SM_BAR+32+(seg&1)*8; mbar_expect_tx(mb,32768);
      const int c0=3*(int)r2, c1=(r2==2)? 8: c0+3;
      for(int c=c0;c<c1;c++) tma_x_mc(sb2+SM_X+(seg&1)*32768+c*4096,&tmx,c*64,seg*32,mb); };
    if(tid==0&&blockIdx.x==0) STAMP(23);
    mbar_wait(mbX,0);
    if(tid==0&&blockIdx.x==0) STAMP(24);
    shadow_issue1(0); shadow_issue2(0); shadow_epi(0);
    if(tid==0&&blockIdx.x==0) STAMP(25);
    asm volatile("barrier.cluster.wait.acquire.aligned;":::"memory");
    if(tid==0&&blockIdx.x==0) STAMP(26);
    bar_sync(10,256); if(tid==160){ shadow_send(0); shadow_export(0); }
    if(tid==96){ for(int i=0;i<8;i++) sch[i]=0; }
    __syncwarp();
    for(int s=0;s<NSEG;s++){
            TLSETUP
      const bool shad=(s+1<NSEG);
      if(shad) mbar_wait(mbX+((s+1)&1)*8,((s+1)>>1)&1);
      if(s>0) bar_sync(9,384);
      if(warp==4) TL(10);
      shadow_issue1(s+1); shadow_issue2(s+1);
      if(warp==4) TL(11);
      shadow_epi(s+1);
      if(warp==4) TL(12);
      bar_sync(1,384);
      float a0[4]={0,0,0,0}, a1[4]={0,0,0,0};
      { uint32_t b[3][4];
        if(warp==4) TL(13);
        ldsm4t(b[0],ma); ldsm4t(b[1],ma+512);
        #pragma unroll
        for(int kk=0;kk<16;kk++){
          const int nx=kk+2;
          if(nx==4) bar_sync(2,384); else if(nx==8) bar_sync(3,384); else if(nx==12) bar_sync(4,384);
          if(nx<16) ldsm4t(b[nx%3],ma+nx*512);
          mma_bf16(a0,w[kk*8],w[kk*8+1],w[kk*8+2],w[kk*8+3],b[kk%3][0],b[kk%3][1]);
          mma_bf16(a1,w[kk*8+4],w[kk*8+5],w[kk*8+6],w[kk*8+7],b[kk%3][2],b[kk%3][3]);
        } }
      if(warp==4) TL(14);
      float sc=misc[0];
      uint32_t w0=pack_bf16((a0[0]+a1[0])*sc,(a0[1]+a1[1])*sc), w1=pack_bf16((a0[2]+a1[2])*sc,(a0[3]+a1[3])*sc);
      { uint32_t so=(s&1)*8192, mo=(s&1)*8;
        if(s<NSEG-1){ st_async1(dq1+so,w0,dm1+mo); st_async1(dq2+so,w0,dm2+mo); st_async1(dq1+so+128,w1,dm1+mo); st_async1(dq2+so+128,w1,dm2+mo); }
        sts32(dql+so,w0); sts32(dql+so+128,w1);
        __syncwarp(); if(lane==0 && s<NSEG-1) mbar_arrive(mbA+mo);
        asm volatile("fence.proxy.async.shared::cta;":::"memory"); }
      if(warp==5) bar_sync(12,256); else bar_arrive(12,256);
      if(warp==4) TL(15);
      if(warp<ntile-8 && s<NSEG-1){
        if(s==0) bar_sync(14,128+32*(ntile-8));
        const uint32_t l16=opq(sb)+lane*16; const uint32_t aw=l16+SM_T5C+warp*4096, ao=l16+SM_O;
        uint32_t f0[4],f1[4],f2[4],f3[4];
        lds128u(f0,aw); lds128u(f1,aw+512); lds128u(f2,aw+1024); lds128u(f3,aw+1536);
        const uint32_t ln=opq(lane); char* ra=(char*)g_acc+(size_t)(4*(11*(int)r+8+warp)+(ln>>4))*256+(((ln>>2)&3)*4+(ln&3))*8+(s&3)*32768;
        bar_sync(7,128+32*(ntile-8));
        float x[4]={0,0,0,0}, y[4]={0,0,0,0}; uint32_t o0[4],o1[4];
        ldsm4t(o0,ao); ldsm4t(o1,ao+512);
        mma_bf16(x,f0[0],f0[1],f0[2],f0[3],o0[0],o0[1]); mma_bf16(y,f1[0],f1[1],f1[2],f1[3],o0[2],o0[3]);
        lds128u(f0,aw+2048); lds128u(f1,aw+2560); ldsm4t(o0,ao+1024);
        mma_bf16(x,f2[0],f2[1],f2[2],f2[3],o1[0],o1[1]); mma_bf16(y,f3[0],f3[1],f3[2],f3[3],o1[2],o1[3]);
        lds128u(f2,aw+3072); lds128u(f3,aw+3584); ldsm4t(o1,ao+1536);
        mma_bf16(x,f0[0],f0[1],f0[2],f0[3],o0[0],o0[1]); mma_bf16(y,f1[0],f1[1],f1[2],f1[3],o0[2],o0[3]);
        mma_bf16(x,f2[0],f2[1],f2[2],f2[3],o1[0],o1[1]); mma_bf16(y,f3[0],f3[1],f3[2],f3[3],o1[2],o1[3]);
        put_red(ra,x,y);
        if(warp==0) TL(16);
        if(tid==0) red_max_u32((char*)g_acc+(s&3)*32768+(blockIdx.x&15)*256+128,gtime32()); }
      if(warp==3 && s>=1){
        unsigned tsv=0, fl=0; if(lane<16){ tsv=ld_relaxed_u32(accb+((s-1)&3)*32768+lane*256+128); fl=ld_relaxed_u32(accb+((s-1)&3)*32768+lane*256+132); }
        tsv=__reduce_max_sync(~0u,tsv); fl=__reduce_max_sync(~0u,fl);
        if(lane==0){
          unsigned Gp=sch[0], L1=sch[1], L2=sch[2], L3=sch[3], Ra=sch[5], Rb=sch[6];
          if(s==1){ L1=L2=L3=p.lam0; }
          if(s>=3 && !fl){
            unsigned Reff=Ra; if((int)(Gp+p.d0-Reff)>0) Reff=Gp+p.d0;
            L3=L2; L2=L1; L1=tsv-Reff; }
          const unsigned Lm=max(min(L1,L2),min(max(L1,L2),L3));
          unsigned Rs=(s>=2)? Rb : tsv+p.d0; if((int)(tsv+p.d0-Rs)>0) Rs=tsv+p.d0;
          const unsigned R=Rs+Lm+p.d0+(fl? p.fpen:0u);
          sch[0]=tsv; sch[1]=L1; sch[2]=L2; sch[3]=L3; sch[5]=Rb; sch[6]=R; sch[7]=R;
          if(blockIdx.x==0) asm volatile("st.relaxed.gpu.global.u32 [%0],%1;"::"l"(&g_ctrl.rpub),"r"(s+3<NSEG? R : R-1000000u):"memory"); }
        __syncwarp(); }
      if(tid==96&&blockIdx.x==0) STAMP(100+s);
      if(tid==160){
        if(s>0){ asm volatile("cp.async.bulk.wait_group 0;":::"memory"); fence_gpu(); red_add_u32(&g_ctrl.segflag[(s-1)*8],1); }
        if(shad) mbar_wait(mbA+(s&1)*8,(s>>1)&1);
        if(shad) shadow_export(s+1);
        km_export(s);
        if(s==0){ x_load(2); x_load(3); } else if(s+3<NSEG) x_load(s+3);
        if(shad) shadow_send(s+1); }
      if(warp==7 && s>=2){
        int l=opq(blockIdx.x)+96*(lane>>4); if(l<128) *((uint4*)((char*)g_acc+((s-2)&3)*32768+l*256)+(lane&15))=make_uint4(0,0,0,0);
        __threadfence(); }
    }
  } else {
    asm volatile("setmaxnreg.dec.sync.aligned.u32 152;");
    uint32_t w[64];
    asm volatile("barrier.cluster.arrive.relaxed.aligned;":::"memory");
    uint32_t mx0=0, nom0=0;
    {
      const int tau=tid-256;
      #pragma unroll
      for(int j=0;j<8;j++){ int nu=j*128+tau; int d=nu>>1, hf=nu&1; uint32_t v[2];
        #pragma unroll
        for(int i=0;i<2;i++){ uint32_t lo=*(const unsigned short*)(p.mem0+(4*hf+2*i)*DM+d), hi=*(const unsigned short*)(p.mem0+(4*hf+2*i+1)*DM+d); v[i]=lo|(hi<<16); mx0=maxabs_bf2(mx0,v[i]); }
        *(uint2*)(sm+SM_MEM+nu*8)=make_uint2(v[0],v[1]); }
      if(tau==0) misc[0]=1.0f;
      #pragma unroll
      for(int q=0;q<4;q++) bar_arrive(1+q,384);
      { const int ncg=(r==2)? 20:22, cg=tau%22, rg=tau/22; float cs[8];
        #pragma unroll
        for(int i=0;i<8;i++) cs[i]=0.f;
        if(rg<5 && cg<ncg){ const uint4* wp=(const uint4*)(p.Wo+(size_t)h*HE*DM+176*r+cg*8);
          uint4 vv[26];
          #pragma unroll
          for(int q=0;q<26;q++){ const int e=rg+5*q; vv[q]=(e<128)? wp[(size_t)e*(DM/8)] : make_uint4(0,0,0,0); }
          #pragma unroll
          for(int q=0;q<26;q++){ const uint4 v=vv[q];
            cs[0]+=fabsf(bf_lo(v.x)); cs[1]+=fabsf(bf_hi(v.x)); cs[2]+=fabsf(bf_lo(v.y)); cs[3]+=fabsf(bf_hi(v.y)); cs[4]+=fabsf(bf_lo(v.z)); cs[5]+=fabsf(bf_hi(v.z)); cs[6]+=fabsf(bf_lo(v.w)); cs[7]+=fabsf(bf_hi(v.w)); } }
        float* red=(float*)(sm+SM_SX);
        if(rg<5){
          #pragma unroll
          for(int i=0;i<8;i++) red[rg*176+cg*8+i]=cs[i]; }
        bar_sync(8,128);
        float cm=0.f;
        for(int cc2=tau;cc2<176;cc2+=128) cm=fmaxf(cm,((red[cc2]+red[176+cc2])+(red[352+cc2]+red[528+cc2]))+red[704+cc2]);
        nom0=__reduce_max_sync(~0u,__float_as_uint(cm*1.001f)); } }
    { const int u=warp-8; uint32_t w3t[32];
      bar_sync(15,384);
      const int par=((volatile unsigned*)misc)[9];
      if(tid==256){ mbar_expect_tx(mbW+8,49152); for(int j=0;j<3;j++) tma_2d(sb+SM_STO+j*16384,&tmwo,176*(int)r+64*j,h*HE,mbW+8); }
      { unsigned a=(lane<8)? ((volatile unsigned*)misc)[24+lane]:0u, b=(lane<8)? ((volatile unsigned*)misc)[32+lane]:0u; a=__reduce_max_sync(~0u,a); b=__reduce_max_sync(~0u,b);
        if(lane==0){ atom_max_done(&g_ctrl.noh[par][h],nom0,sb+SM_MISC+160+u*4);
          if(u==1) atom_max_done(&g_ctrl.xmax[par],a<<16,sb+SM_MISC+160+u*4); if(u==2 && r==2) atom_max_done(&g_ctrl.nv[par],b,sb+SM_MISC+160+u*4); } }
      __syncwarp();
      bar_sync(8,128);
      if(tid==288){ fence_gpu(); red_add_u32(&g_ctrl.bar_cnt,1); if(blockIdx.x==0) STAMP(28); }
      mbar_wait(mbW+8,0);
      if(tid==256&&blockIdx.x==0) STAMP(27);
      const int er=(lane&7)+8*(lane>>4);
      #pragma unroll
      for(int j=0;j<3;j++){ int T=u+4*j; bool valid=T<ntile; const int c0=16*(valid?T:0)+8*((lane>>3)&1);
        const uint32_t a=sb+SM_STO+(c0>>6)*16384+er*128+((((c0&63)>>3)^(er&7))<<4);
        #pragma unroll
        for(int ks=0;ks<8;ks++){ if(j<2) ldsm4t(&w[j*32+ks*4],a+ks*2048); else ldsm4t(&w3t[ks*4],a+ks*2048); } }
      uint4* cc=(uint4*)(sm+SM_T5C)+u*256+lane;
      #pragma unroll
      for(int ks=0;ks<8;ks++) cc[ks*32]=make_uint4(w3t[ks*4],w3t[ks*4+1],w3t[ks*4+2],w3t[ks*4+3]);
      bar_arrive(14,128+32*(ntile-8));
      asm volatile("barrier.cluster.wait.acquire.aligned;":::"memory");
    }
    const int u=warp-8, tau=tid-256, kap=u>>1, mi=lane>>3, rr=lane&7;
    const float SL2=0.08838834764831845f*1.4426950408889634f;
    const uint32_t L16=pin(sb+lane*16), L4=pin(sb+lane*4);
    const uint32_t cdst=pin(sb+SM_MEM+tau*8);
    const char* lbase=accb+(tau>>3)*256+(tau&7)*16;
    const uint32_t a_q =L16+(SM_QKV+kap*1024);
    const uint32_t a_km=pin(sb+SM_QKV+2048+(64*kap+8*(mi>>1)+rr)*16);
    const uint32_t a_vm=L16+(SM_QKV+4096+u*512);
    const uint32_t a_kx=pin(sb+SM_KV+(64*kap+8*(mi>>1)+rr)*64+(((mi&1)^((rr>>1)&3))<<4));
    const uint32_t a_vx=pin(sb+SM_KV+8192+(32*u+8*(mi&1)+rr)*64+(((mi>>1)^((rr>>1)&3))<<4));
    const uint32_t a_sxw=L16+(SM_SX+u*1536), a_sxr=L16+(SM_SX+(u^2)*1536);
    const uint32_t a_ow=L4+(SM_O+u*512), a_or=L16+SM_O;
    char* redb=(char*)g_acc+(size_t)(4*(11*(int)r+u)+(g>>2))*256+((g&3)*4+t)*8;
    float kscale=1.f; const int obar=128+32*(ntile-8);
    unsigned tred=clk32();
    for(int s=0;s<NSEG;s++){
      uint32_t mx=0;
      TLSETUP
      if(tau==0 && s>0) misc[0]=__uint_as_float(0x7f000000u-__float_as_uint(kscale));
      const char* arb=lbase+((s-1)&3)*32768; asm volatile("":"+l"(arb));
      if(s>0){ if(u==0){ const unsigned Rn=sch[7]; if(Rn){ int c=0; while((int)(gtime32()-Rn)<0 && ++c<8000){} } else { while((int)(clk32()-tred)<p.delay){} } }
        bar_sync(5,128); }
      if(u==0) TL(0);
      uint32_t kx[32];
      auto preload_k=[&](){ mbar_wait(mbKV+(s&1)*8,(s>>1)&1); const uint32_t so=(s&1)*16384;
        #pragma unroll
        for(int kq=0;kq<4;kq++){ ldsm4t(&kx[kq*8],a_kx+so+kq*1024); ldsm4t(&kx[kq*8+4],(a_kx^32)+so+kq*1024); } };
      if(s==0){ mx=mx0;
      } else {
        const char* b=arb;
        uint4 v[8];
        #pragma unroll
        for(int j=0;j<8;j++) v[j]=ld_relaxed_v4(b+j*4096);
        #pragma unroll
        for(int q=0;q<4;q++){ int c=0;
          while(__any_sync(~0u,bad_unit(v[2*q])|bad_unit(v[2*q+1]))){
 if(lane==0) red_max_u32((char*)g_acc+(s&3)*32768+(blockIdx.x&15)*256+132,1u);
 backoff(p.boff);
            #pragma unroll
            for(int j=2*q;j<8;j++) v[j]=ld_relaxed_v4(b+j*4096);
            if(++c>(1<<16)){ g_ctrl.err=3; break; } }
          cvt_unit(v[2*q],cdst+(2*q)*1024,mx); cvt_unit(v[2*q+1],cdst+(2*q+1)*1024,mx);
          bar_arrive(1+q,384); if(u==0){ if(q==0) TL(1); if(q==3) TL(2); } }
      }
      if(s==NSEG-1) break;
      preload_k();
      if(tau==0) mbar_expect_tx(mbA+(s&1)*8,4096);
      mx=max(mx&0x7fffu,(mx>>16)&0x7fffu); mx=__reduce_max_sync(~0u,mx); if(lane==0) ((volatile unsigned*)misc)[16+u]=mx;
      if(s==0 && u==0){ if(blockIdx.x==0&&lane==0) STAMP(29); grid_wait(); if(blockIdx.x==0&&lane==0) STAMP(30); }
      bar_sync(8,128);
      { const float prev_inv=misc[0]; unsigned m4=(lane<4)? ((volatile unsigned*)misc)[16+lane] : 0u; m4=__reduce_max_sync(~0u,m4);
        float mm=__uint_as_float(m4<<16)*prev_inv; float B=fmaxf(mm,misc[10])*misc[8];
        int e=(int)((__float_as_uint(B)>>23)&0xff); int k=127+20-(e-127); k=min(max(k,2),252); kscale=__uint_as_float((unsigned)k<<23); }
      if(u==0) TL(3);
      mbar_wait(mbA+(s&1)*8,(s>>1)&1);
      if(u==0) TL(4);
      const uint32_t qo=(s&1)*8192;
      float s0[4]={0,0,0,0}, s1[4]={0,0,0,0}, s2[4]={0,0,0,0};
      uint32_t qf[8], km[16], vm[4];
      ldsm4t(&qf[0],a_q+qo); ldsm4t(&km[0],a_km+qo); ldsm4t(&km[4],a_km+qo+256); ldsm4t(&qf[4],a_q+qo+512); ldsm4t(&km[8],a_km+qo+512); ldsm4t(&km[12],a_km+qo+768);
      #pragma unroll
      for(int kq=0;kq<4;kq++){
        mma_bf16(s1,kx[kq*8+0],kx[kq*8+1],kx[kq*8+2],kx[kq*8+3],qf[2*kq],qf[2*kq+1]);
        mma_bf16(s2,kx[kq*8+4],kx[kq*8+5],kx[kq*8+6],kx[kq*8+7],qf[2*kq],qf[2*kq+1]);
        mma_bf16(s0,km[kq*4],km[kq*4+1],km[kq*4+2],km[kq*4+3],qf[2*kq],qf[2*kq+1]); }
      sts128f(a_sxw,s1[0],s1[1],s1[2],s1[3]); sts128f(a_sxw+512,s2[0],s2[1],s2[2],s2[3]); sts128f(a_sxw+1024,s0[0],s0[1],0.f,0.f);
      ldsm4(vm,a_vm+qo);
      if(u==0) TL(5);
      bar_sync(6,128);
      { float4 o1=lds128f(a_sxr), o2=lds128f(a_sxr+512), o0=lds128f(a_sxr+1024);
        s1[0]+=o1.x; s1[1]+=o1.y; s1[2]+=o1.z; s1[3]+=o1.w; s2[0]+=o2.x; s2[1]+=o2.y; s2[2]+=o2.z; s2[3]+=o2.w; s0[0]+=o0.x; s0[1]+=o0.y; }
      uint32_t vx[16];
      { const uint32_t so=(s&1)*16384;
        #pragma unroll
        for(int j=0;j<2;j++){ ldsm4(&vx[j*8],a_vx+so+j*1024); ldsm4(&vx[j*8+4],(a_vx^32)+so+j*1024); } }
      float mA=fmaxf(fmaxf(fmaxf(s1[0],s1[2]),fmaxf(s2[0],s2[2])),s0[0]), mB=fmaxf(fmaxf(fmaxf(s1[1],s1[3]),fmaxf(s2[1],s2[3])),s0[1]);
      #pragma unroll
      for(int o=4;o<32;o<<=1){ mA=fmaxf(mA,__shfl_xor_sync(~0u,mA,o)); mB=fmaxf(mB,__shfl_xor_sync(~0u,mB,o)); }
      float nA=-mA*SL2, nB=-mB*SL2;
      float p00=ex2(fmaf(s0[0],SL2,nA)), p01=ex2(fmaf(s0[1],SL2,nB));
      float p10=ex2(fmaf(s1[0],SL2,nA)), p11=ex2(fmaf(s1[1],SL2,nB)), p12=ex2(fmaf(s1[2],SL2,nA)), p13=ex2(fmaf(s1[3],SL2,nB));
      float p20=ex2(fmaf(s2[0],SL2,nA)), p21=ex2(fmaf(s2[1],SL2,nB)), p22=ex2(fmaf(s2[2],SL2,nA)), p23=ex2(fmaf(s2[3],SL2,nB));
      uint32_t b0=movm_t(pack_bf16(p00,p01)), b10=movm_t(pack_bf16(p10,p11)), b11=movm_t(pack_bf16(p12,p13)), b20=movm_t(pack_bf16(p20,p21)), b21=movm_t(pack_bf16(p22,p23));
      float sA=(p10+p12)+(p20+p22)+p00, sB=(p11+p13)+(p21+p23)+p01;
      float o0[4]={0,0,0,0}, o1[4]={0,0,0,0};
      mma_k8(o0,vm[0],vm[1],b0); mma_k8(o1,vm[2],vm[3],b0);
      mma_bf16(o0,vx[0],vx[1],vx[2],vx[3],b10,b11); mma_bf16(o1,vx[8],vx[9],vx[10],vx[11],b10,b11);
      mma_bf16(o0,vx[4],vx[5],vx[6],vx[7],b20,b21); mma_bf16(o1,vx[12],vx[13],vx[14],vx[15],b20,b21);
      #pragma unroll
      for(int o=4;o<32;o<<=1){ sA+=__shfl_xor_sync(~0u,sA,o); sB+=__shfl_xor_sync(~0u,sB,o); }
      float iA=__fdividef(kscale,sA), iB=__fdividef(kscale,sB);
      if(u==0) TL(6);
      sts32(a_ow,pack_bf16(o0[0]*iA,o0[1]*iB)); sts32(a_ow+128,pack_bf16(o0[2]*iA,o0[3]*iB)); sts32(a_ow+256,pack_bf16(o1[0]*iA,o1[1]*iB)); sts32(a_ow+384,pack_bf16(o1[2]*iA,o1[3]*iB));
      bar_sync(7,obar);
      if(u==0) TL(7);
      uint32_t ob[16];
      #pragma unroll
      for(int kk=0;kk<4;kk++) ldsm4t(&ob[kk*4],a_or+kk*512);
      char* ra=redb+(s&3)*32768;
      { float x[4]={0,0,0,0}, y[4]={0,0,0,0}, x2[4]={0,0,0,0}, y2[4]={0,0,0,0};
        #pragma unroll
        for(int ks=0;ks<8;ks+=2){
          mma_bf16(x,w[ks*4],w[ks*4+1],w[ks*4+2],w[ks*4+3],ob[ks*2],ob[ks*2+1]); mma_bf16(y,w[ks*4+4],w[ks*4+5],w[ks*4+6],w[ks*4+7],ob[ks*2+2],ob[ks*2+3]);
          mma_bf16(x2,w[32+ks*4],w[32+ks*4+1],w[32+ks*4+2],w[32+ks*4+3],ob[ks*2],ob[ks*2+1]); mma_bf16(y2,w[32+ks*4+4],w[32+ks*4+5],w[32+ks*4+6],w[32+ks*4+7],ob[ks*2+2],ob[ks*2+3]); }
        put_red(ra,x,y); put_red(ra+4096,x2,y2); }
      if(u==0) TL(8);
      bar_arrive(9,384);
      tred=clk32();
      if(tid==256) red_max_u32((char*)g_acc+(s&3)*32768+(blockIdx.x&15)*256+128,gtime32());
    }
  }
  if(tid==160){ asm volatile("cp.async.bulk.wait_group 0;":::"memory"); fence_gpu(); red_add_u32(&g_ctrl.segflag[(NSEG-1)*8],1); if(blockIdx.x==0) STAMP(1); }
  asm volatile("barrier.cluster.arrive.release.aligned; barrier.cluster.wait.acquire.aligned;":::"memory");
}

constexpr int PA_UP=6544;
constexpr int PA_WW=2064;
constexpr int PA_SM_RAW=0;
constexpr int PA_SM_U=65536;
constexpr int PA_SM_W=PA_SM_U+8*PA_UP;
constexpr int PA_SM_KC=PA_SM_W+8*PA_WW*4;
constexpr int PA_SM_PAR=PA_SM_KC+8*644*4;
constexpr int PA_SM_IDX=PA_SM_PAR+8*2048;
constexpr int PA_SM_TOTAL=PA_SM_IDX+4096;

__device__ __forceinline__ void mma_tf32(float* d,uint32_t a0,uint32_t a1,uint32_t a2,uint32_t a3,uint32_t b0,uint32_t b1){
  asm volatile("mma.sync.aligned.m16n8k8.row.col.f32.tf32.tf32.f32 {%0,%1,%2,%3},{%4,%5,%6,%7},{%8,%9},{%0,%1,%2,%3};":"+f"(d[0]),"+f"(d[1]),"+f"(d[2]),"+f"(d[3]):"r"(a0),"r"(a1),"r"(a2),"r"(a3),"r"(b0),"r"(b1)); }
struct cf { float r,i; };
__device__ __forceinline__ uint32_t fb(float x){ return __float_as_uint(x); }
__device__ __forceinline__ cf cmul(cf a,cf b){ cf c; c.r=fmaf(a.r,b.r,-a.i*b.i); c.i=fmaf(a.r,b.i,a.i*b.r); return c; }
__device__ __forceinline__ cf cmulc(cf a,cf b){ cf c; c.r=fmaf(a.r,b.r,-a.i*b.i); c.i=fmaf(-a.r,b.i,-a.i*b.r); return c; }
__device__ __forceinline__ cf csq(cf a){ cf c; c.r=fmaf(a.r,a.r,-a.i*a.i); c.i=2.f*a.r*a.i; return c; }
__device__ __forceinline__ cf cexpm(float zr2,float zi,float m){
  float e=ex2(zr2*m); float th=zi*m; float k=fmaf(th,0.15915494309189535f,12582912.f)-12582912.f; th=fmaf(k,-6.2831854820251465f,th); th=fmaf(k,1.7484555314695172e-7f,th);
  cf c; c.r=e*__cosf(th); c.i=e*__sinf(th); return c; }

template<int MB> __device__ __forceinline__ void pa_conv_block(float (&acc)[16][4],uint32_t aw,uint32_t au){
  #pragma unroll 1
  for(int mo=0;mo<8;mo++){
    const int m=16*MB+mo;
    uint32_t p0,p1,pm,q0,q1;
    const uint32_t a=aw+m*64;
    asm volatile("ld.shared.b32 %0,[%1];":"=r"(p0):"r"(a)); asm volatile("ld.shared.b32 %0,[%1+32];":"=r"(p1):"r"(a)); asm volatile("ld.shared.b32 %0,[%1+-32];":"=r"(pm):"r"(a));
    uint32_t qm; asm volatile("ld.shared.b32 %0,[%1+512];":"=r"(q0):"r"(a)); asm volatile("ld.shared.b32 %0,[%1+544];":"=r"(q1):"r"(a)); asm volatile("ld.shared.b32 %0,[%1+480];":"=r"(qm):"r"(a));
    const uint32_t ub=au-m*48;
    #pragma unroll
    for(int I=2*MB;I<16;I+=2){
      uint32_t b[4]; ldsm4(b,ub+I*8*48);
      mma_bf16(acc[I],p0,p1,pm,p0,b[0],b[1]);
      mma_bf16(acc[I+1],q0,q1,qm,q0,b[0],b[1]);
      mma_bf16(acc[I+1],p0,p1,pm,p0,b[2],b[3]);
      if(I+2<16) mma_bf16(acc[I+2],q0,q1,qm,q0,b[2],b[3]);
    }
  }
}

__device__ __forceinline__ void partA_cta(unsigned char* sm,int task,const bf16* __restrict__ u,const bf16* __restrict__ Are,const bf16* __restrict__ Aim,const bf16* __restrict__ Bre,const bf16* __restrict__ Bim,
    const bf16* __restrict__ Cre,const bf16* __restrict__ Cim,const bf16* __restrict__ logdt,const bf16* __restrict__ Dsk,bf16* __restrict__ out){
  const uint32_t sb=smem_u32(sm);
  const int tid=threadIdx.x, warp=tid>>5, lane=tid&31, g=lane>>2, t=lane&3;
  const int d0=task*16;
  for(int c=tid;c<4096;c+=256){ int row=c>>1, hf=c&1; cp16(sb+PA_SM_RAW+row*32+hf*16, u+(size_t)row*DM+d0+hf*8); }
  asm volatile("cp.async.commit_group;":::"memory");
  for(int x=tid;x<2048;x+=256){ int lb=(int)__bfloat162float(__float2bfloat16_rn((float)x)); int idx; if(lb<256) idx=lb; else { int r=(31-__clz(lb))-7; idx=(lb==2048)? 640 : 128*(1+r)+((lb>>r)-128); } ((unsigned short*)(sm+PA_SM_IDX))[x]=(unsigned short)idx; }
  { uint32_t* z=(uint32_t*)(sm+PA_SM_U+warp*PA_UP); for(int i=lane;i<96;i+=32) z[i]=0; }
  for(int rnd=0;rnd<2;rnd++){
    const int d=d0+rnd*8+warp;
    { const float dt=__bfloat162float(__float2bfloat16_rn(expf(__bfloat162float(logdt[d]))));
      float4* par=(float4*)(sm+PA_SM_PAR+warp*2048);
      #pragma unroll
      for(int j=0;j<4;j++){ int n=j*32+lane; size_t o=(size_t)d*128+n;
        float ar=dt*__bfloat162float(Are[o]), ai=dt*__bfloat162float(Aim[o]), br=dt*__bfloat162float(Bre[o]), bi=dt*__bfloat162float(Bim[o]), cr=__bfloat162float(Cre[o]), ci=__bfloat162float(Cim[o]);
        const float TB=1.000704f;
        par[n]=make_float4(ar*1.4426950408889634f,ai,(cr*br-ci*bi)*TB,(cr*bi+ci*br)*TB); } }
    __syncwarp();
    { float k0[4]={0,0,0,0},k1[4]={0,0,0,0},k2[4]={0,0,0,0},k3[4]={0,0,0,0},k4[4]={0,0,0,0},k5[4]={0,0,0,0};
      const float4* par=(const float4*)(sm+PA_SM_PAR+warp*2048);
      const float fg=(float)g;
      #pragma unroll 2
      for(int ks=0;ks<32;ks++){
        const float4 pz=par[ks*4+t]; cf W; W.r=pz.z; W.i=pz.w;
        const cf l0=cexpm(pz.x,pz.y,fg), l1=csq(l0), l2=csq(l1), ha=csq(l2);
        cf c32; c32.r=__shfl_sync(~0u,ha.r,16+t); c32.i=__shfl_sync(~0u,ha.i,16+t);
        const cf c64=csq(c32), c128=csq(c64);
        const cf hb=cmul(ha,c64); cf hc=cmul(ha,c128), hd=cmul(hb,c128);
        cf b=cmulc(W,l0);
        mma_tf32(k0,fb(ha.r),fb(hb.r),fb(ha.i),fb(hb.i),fb(b.r),fb(b.i));
        mma_tf32(k1,fb(hc.r),fb(hd.r),fb(hc.i),fb(hd.i),fb(b.r),fb(b.i));
        hc=csq(hc); hd=csq(hd); b=cmulc(W,l1);
        mma_tf32(k2,fb(hc.r),fb(hd.r),fb(hc.i),fb(hd.i),fb(b.r),fb(b.i));
        hc=csq(hc); hd=csq(hd); b=cmulc(W,l2);
        mma_tf32(k3,fb(hc.r),fb(hd.r),fb(hc.i),fb(hd.i),fb(b.r),fb(b.i));
        hc=csq(hc); hd=csq(hd); b=cmulc(W,ha);
        mma_tf32(k4,fb(hc.r),fb(hd.r),fb(hc.i),fb(hd.i),fb(b.r),fb(b.i));
        const cf e=csq(hc);
        mma_tf32(k5,fb(e.r),0u,fb(e.i),0u,fb(b.r),fb(b.i));
      }
      float* kc=(float*)(sm+PA_SM_KC+warp*644*4);
      *(float2*)(kc+0*128+8*g+2*t)=make_float2(k0[0],k0[1]); *(float2*)(kc+0*128+8*(g+8)+2*t)=make_float2(k0[2],k0[3]);
      *(float2*)(kc+1*128+8*g+2*t)=make_float2(k1[0],k1[1]); *(float2*)(kc+1*128+8*(g+8)+2*t)=make_float2(k1[2],k1[3]);
      *(float2*)(kc+2*128+8*g+2*t)=make_float2(k2[0],k2[1]); *(float2*)(kc+2*128+8*(g+8)+2*t)=make_float2(k2[2],k2[3]);
      *(float2*)(kc+3*128+8*g+2*t)=make_float2(k3[0],k3[1]); *(float2*)(kc+3*128+8*(g+8)+2*t)=make_float2(k3[2],k3[3]);
      *(float2*)(kc+4*128+8*g+2*t)=make_float2(k4[0],k4[1]); *(float2*)(kc+4*128+8*(g+8)+2*t)=make_float2(k4[2],k4[3]);
      if(lane==0) kc[640]=k5[0]; }
    if(rnd==0){ asm volatile("cp.async.wait_group 0;":::"memory"); }
    bar_sync(11,256);
    { const float* kc=(const float*)(sm+PA_SM_KC+warp*644*4); uint32_t* Wt=(uint32_t*)(sm+PA_SM_W+warp*PA_WW*4)+16; const unsigned short* ix=(const unsigned short*)(sm+PA_SM_IDX);
      if(lane<16) Wt[lane-16]=0;
      #pragma unroll 4
      for(int i=0;i<32;i++){ const int x=i*64+2*lane; const uint32_t i2=*(const uint32_t*)(ix+x); const float v0=kc[i2&0xffff], v1=kc[i2>>16]; const float vm=(x>0)? kc[ix[x-1]] : 0.f;
        *(uint2*)(Wt+x)=make_uint2(pack_bf16(v0,vm),pack_bf16(v1,v0)); } }
    { const uint32_t ar=sb+PA_SM_RAW+rnd*16+lane*32;
      #pragma unroll 2
      for(int i=0;i<8;i++){ int t0=(warp*8+i)*32; uint32_t r4[4]; ldsm4t(r4,ar+t0*32);
        #pragma unroll
        for(int j=0;j<4;j++){ int tt=t0+8*j+2*t; sts32(sb+PA_SM_U+g*PA_UP+(8+(tt>>4))*48+(tt&15)*2,r4[j]); } } }
    bar_sync(11,256);
    float acc[16][4];
    #pragma unroll
    for(int I=0;I<16;I++){ acc[I][0]=acc[I][1]=acc[I][2]=acc[I][3]=0.f; }
    { const uint32_t aw=sb+PA_SM_W+warp*PA_WW*4+(16+g-2*t)*4;
      const uint32_t au=sb+PA_SM_U+warp*PA_UP+8*48+(lane&7)*48+((lane>>3)&1)*16+(lane>>4)*8*48;
      pa_conv_block<0>(acc,aw,au); pa_conv_block<1>(acc,aw,au); pa_conv_block<2>(acc,aw,au); pa_conv_block<3>(acc,aw,au);
      pa_conv_block<4>(acc,aw,au); pa_conv_block<5>(acc,aw,au); pa_conv_block<6>(acc,aw,au); pa_conv_block<7>(acc,aw,au); }
    __syncwarp();
    { const uint32_t ay=sb+PA_SM_W+warp*PA_WW*4+(lane&7)*48+((lane>>3)&1)*16+(lane>>4)*8*48;
      #pragma unroll
      for(int I=0;I<16;I+=2)
        asm volatile("stmatrix.sync.aligned.m8n8.x4.trans.shared.b16 [%0],{%1,%2,%3,%4};"::"r"(ay+I*8*48),"r"(pack_bf16(acc[I][0],acc[I][1])),"r"(pack_bf16(acc[I][2],acc[I][3])),"r"(pack_bf16(acc[I+1][0],acc[I+1][1])),"r"(pack_bf16(acc[I+1][2],acc[I+1][3])):"memory"); }
    bar_sync(11,256);
    { const __nv_bfloat16 dk=Dsk[d0+rnd*8+g]; const __nv_bfloat162 dk2=__halves2bfloat162(dk,dk);
      #pragma unroll 2
      for(int i=0;i<8;i++){ int t0=(warp*8+i)*32; uint32_t r4[4];
        #pragma unroll
        for(int j=0;j<4;j++){ int tt=t0+8*j+2*t; uint32_t yw=*(const uint32_t*)(sm+PA_SM_W+g*PA_WW*4+(tt>>4)*48+(tt&15)*2), uw=*(const uint32_t*)(sm+PA_SM_U+g*PA_UP+(8+(tt>>4))*48+(tt&15)*2);
          __nv_bfloat162 sk=__hmul2(*(__nv_bfloat162*)&uw,dk2); __nv_bfloat162 y2=__hadd2(*(__nv_bfloat162*)&yw,sk); r4[j]=*(uint32_t*)&y2; }
        asm volatile("stmatrix.sync.aligned.m8n8.x4.trans.shared.b16 [%0],{%1,%2,%3,%4};"::"r"(sb+PA_SM_RAW+rnd*16+(t0+lane)*32),"r"(r4[0]),"r"(r4[1]),"r"(r4[2]),"r"(r4[3]):"memory"); } }
    bar_sync(11,256);
  }
  for(int c=tid;c<4096;c+=256){ int row=c>>1, hf=c&1; *(uint4*)(out+(size_t)row*1024+d0+hf*8)=*(const uint4*)(sm+PA_SM_RAW+row*32+hf*16); }
}
constexpr int HK_XA=0;
constexpr int HK_XSLOT=28672;
constexpr int HK_ST=57344;
constexpr int HK_OT=66560;
constexpr int HK_FN=HK_OT+65536;
constexpr int HK_BAR=PA_SM_TOTAL;
constexpr int HK_TOTAL=HK_BAR+144;
constexpr int PRING=8;
__device__ __align__(128) float g_pex[PRING*8*SEG*DM];
struct HelpP { const bf16 *u,*Are,*Aim,*Bre,*Bim,*Cre,*Cim,*logdt,*Dsk,*Wo; bf16* out; int mode; unsigned w0,w1; };

__global__ void __launch_bounds__(512,1) helper_kernel(const HelpP p,const __grid_constant__ CUtensorMap tmo){
  extern __shared__ __align__(1024) unsigned char sm[];
  const uint32_t sb=smem_u32(sm);
  const int tid=threadIdx.x, warp=__shfl_sync(0xffffffffu,tid>>5,0), lane=tid&31, g=lane>>2, t=lane&3;
  const int c=blockIdx.x, hg=c>>2, cb=c&3;
  const uint32_t mbXF=sb+HK_BAR, mbXE=mbXF+16, mbOF=mbXF+32, mbOE=mbXF+48, mbFN=mbXF+64, cntO=mbXF+80, cntP=mbXF+84;
  if(tid==0){ for(int i=0;i<2;i++){ mbar_init(mbXF+8*i,1); mbar_init(mbXE+8*i,4); mbar_init(mbOF+8*i,1); mbar_init(mbOE+8*i,8); }
    *(volatile unsigned*)(sm+HK_BAR+80)=0; *(volatile unsigned*)(sm+HK_BAR+84)=0;
    mbar_init(mbFN,1); mbar_init(mbFN+8,1);
    asm volatile("fence.mbarrier_init.release.cluster;":::"memory"); }
  if(tid==0&&blockIdx.x==0) STAMP(2);
  const unsigned E=ld_relaxed_u32(&g_ctrl.start_cnt)/96;
  if(warp<8){
    asm volatile("setmaxnreg.inc.sync.aligned.u32 176;");
    if(!(p.mode&1)) partA_cta(sm,c,p.u,p.Are,p.Aim,p.Bre,p.Bim,p.Cre,p.Cim,p.logdt,p.Dsk,p.out);
    bar_sync(11,256);
    if(tid==0&&blockIdx.x==0) STAMP(3);
    { const bf16* W=p.Wo+(size_t)hg*512*DM+cb*128;
      for(int i=tid;i<8192;i+=256){ int row=i>>4, col=i&15; cp16(sb+row*WPITCH+col*16, W+(size_t)row*DM+col*8); }
      asm volatile("cp.async.commit_group; cp.async.wait_group 0;":::"memory"); }
    bar_sync(11,256);
    uint32_t w[128];
    { uint32_t a=sb+((lane&7)+8*(lane>>4))*WPITCH+(16*warp+8*((lane>>3)&1))*2;
      #pragma unroll
      for(int ks=0;ks<32;ks++) ldsm4t(&w[ks*4],a+ks*16*WPITCH); }
    asm volatile("{ .reg .pred p; setp.eq.u32 p,%0,0x7fc1dead; @p st.shared.u32 [%1],%0; }"::"r"(w[127]^w[126]),"r"(sb+HK_BAR+96):"memory");
    bar_sync(0,512);
    if(tid==0&&blockIdx.x==0) STAMP(4);
    float sa[16];
    float* const Pb=g_pex+(size_t)cb*32768+(t>>1)*4096+hg*512+(2*(t&1))*128+16*warp+g;
    for(int s=0;s<NSEG;s++){
      mbar_wait(mbOF+(s&1)*8,(s>>1)&1);
      if(tid==0&&c==0) STAMP(700+s);
      { const uint32_t dlo=(((sb+HK_OT+(s&1)*32768)&0x3FFFF)>>4)|(1u<<16);
        wg_fence(); ShadowRange<0,32>::run(sa,w,dlo); wg_commit(); wg_wait0(); }
      if(tid==0&&c==0) STAMP(800+s);
      __syncwarp(); if(lane==0) mbar_arrive(mbOE+(s&1)*8);
      if(s>=PRING){ if(lane==0){ int c3=0; while((int)(ld_relaxed_u32(&g_ctrl.fcnt[(s-PRING)*8+cb])-8*E)<0){ __nanosleep(100); if(++c3>(1<<24)){ g_ctrl.err=23; break; } } } __syncwarp(); }
      if(!(p.mode&8)) { float* P=Pb+(size_t)(s&(PRING-1))*(8*SEG*DM);
        #pragma unroll
        for(int j=0;j<4;j++){ P[j*8192]=sa[4*j]; P[j*8192+128]=sa[4*j+1]; P[j*8192+8]=sa[4*j+2]; P[j*8192+136]=sa[4*j+3]; } }
      __syncwarp(); if(lane==0) smem_inc_release(cntP);
      if(tid==0&&blockIdx.x==0) STAMP(200+s);
    }
  } else if(warp<12){
    asm volatile("setmaxnreg.dec.sync.aligned.u32 120;");
    bar_sync(0,512);
    const int j=warp-8, mi=lane>>3, rr=lane&7, h=c;
    const float SL2=0.08838834764831845f*1.4426950408889634f;
    for(int s=0;s<NSEG;s++){
      mbar_wait(mbXF+(s&1)*8,(s>>1)&1);
      const uint32_t b=sb+HK_XA+(s&1)*HK_XSLOT;
      float s0[4]={0,0,0,0}, s1[4]={0,0,0,0}, s2[4]={0,0,0,0};
      const uint32_t aq=b+lane*64+((j^((lane>>1)&3))<<4);
      const uint32_t ak=b+8192+(8*(mi>>1)+rr)*64+(((mi&1)^((rr>>1)&3))<<4);
      const uint32_t am=b+24576+(8*(mi>>1)+rr)*16;
      #pragma unroll
      for(int kk=0;kk<4;kk++){ uint32_t qf[4]; ldsm4t(qf,aq+kk*2048);
        #pragma unroll
        for(int z=0;z<2;z++){ const int ks=2*kk+z; uint32_t k1[4],k2[4],km[4];
          ldsm4t(k1,ak+ks*1024); ldsm4t(k2,(ak^32)+ks*1024); ldsm4t(km,am+ks*256);
          mma_bf16(s1,k1[0],k1[1],k1[2],k1[3],qf[2*z],qf[2*z+1]); mma_bf16(s2,k2[0],k2[1],k2[2],k2[3],qf[2*z],qf[2*z+1]); mma_bf16(s0,km[0],km[1],km[2],km[3],qf[2*z],qf[2*z+1]); } }
      const int qA=8*j+2*t, qB=qA+1; const float NEG=-INFINITY;
      if(g>qA) s1[0]=NEG; if(g>qB) s1[1]=NEG; if(g+8>qA) s1[2]=NEG; if(g+8>qB) s1[3]=NEG;
      if(g+16>qA) s2[0]=NEG; if(g+16>qB) s2[1]=NEG; if(g+24>qA) s2[2]=NEG; if(g+24>qB) s2[3]=NEG;
      float mA=fmaxf(fmaxf(fmaxf(s1[0],s1[2]),fmaxf(s2[0],s2[2])),s0[0]), mB=fmaxf(fmaxf(fmaxf(s1[1],s1[3]),fmaxf(s2[1],s2[3])),s0[1]);
      #pragma unroll
      for(int o=4;o<32;o<<=1){ mA=fmaxf(mA,__shfl_xor_sync(~0u,mA,o)); mB=fmaxf(mB,__shfl_xor_sync(~0u,mB,o)); }
      const float nA=-mA*SL2, nB=-mB*SL2;
      float p00=ex2(fmaf(s0[0],SL2,nA)), p01=ex2(fmaf(s0[1],SL2,nB));
      float p10=ex2(fmaf(s1[0],SL2,nA)), p11=ex2(fmaf(s1[1],SL2,nB)), p12=ex2(fmaf(s1[2],SL2,nA)), p13=ex2(fmaf(s1[3],SL2,nB));
      float p20=ex2(fmaf(s2[0],SL2,nA)), p21=ex2(fmaf(s2[1],SL2,nB)), p22=ex2(fmaf(s2[2],SL2,nA)), p23=ex2(fmaf(s2[3],SL2,nB));
      const uint32_t b0=movm_t(pack_bf16(p00,p01)), b10=movm_t(pack_bf16(p10,p11)), b11=movm_t(pack_bf16(p12,p13)), b20=movm_t(pack_bf16(p20,p21)), b21=movm_t(pack_bf16(p22,p23));
      float sA=(p10+p12)+(p20+p22)+p00, sB=(p11+p13)+(p21+p23)+p01;
      #pragma unroll
      for(int o=4;o<32;o<<=1){ sA+=__shfl_xor_sync(~0u,sA,o); sB+=__shfl_xor_sync(~0u,sB,o); }
      const float iA=__fdividef(1.f,sA), iB=__fdividef(1.f,sB);
      const uint32_t av=b+16384+(8*(mi&1)+rr)*64+(((mi>>1)^((rr>>1)&3))<<4), avm=b+26624+lane*16;
      const uint32_t ast=sb+HK_ST+(8*j+rr)*272+mi*16;
      #pragma unroll
      for(int ip=0;ip<4;ip++){
        uint32_t vm[4],va[4],vb[4],vc[4],vd[4]; ldsm4(vm,avm+ip*512); ldsm4(va,av+ip*2048); ldsm4(vb,(av^32)+ip*2048); ldsm4(vc,av+ip*2048+1024); ldsm4(vd,(av^32)+ip*2048+1024);
        float o0[4]={0,0,0,0}, o1[4]={0,0,0,0};
        mma_k8(o0,vm[0],vm[1],b0); mma_k8(o1,vm[2],vm[3],b0);
        mma_bf16(o0,va[0],va[1],va[2],va[3],b10,b11); mma_bf16(o1,vc[0],vc[1],vc[2],vc[3],b10,b11);
        mma_bf16(o0,vb[0],vb[1],vb[2],vb[3],b20,b21); mma_bf16(o1,vd[0],vd[1],vd[2],vd[3],b20,b21);
        asm volatile("stmatrix.sync.aligned.m8n8.x4.trans.shared.b16 [%0],{%1,%2,%3,%4};"::"r"(ast+ip*64),
          "r"(pack_bf16(o0[0]*iA,o0[1]*iB)),"r"(pack_bf16(o0[2]*iA,o0[3]*iB)),"r"(pack_bf16(o1[0]*iA,o1[1]*iB)),"r"(pack_bf16(o1[2]*iA,o1[3]*iB)):"memory"); }
      __syncwarp(); if(lane==0) mbar_arrive(mbXE+(s&1)*8);
      #pragma unroll
      for(int i=0;i<4;i++){ const int row=8*j+2*i+(lane>>4), cc=lane&15; if(!(p.mode&128)) *(uint4*)(g_o+(size_t)(s*32+row)*(NH*HE)+h*HE+cc*8)=*(const uint4*)(sm+HK_ST+row*272+cc*16); }
      __syncwarp(); if(lane==0) smem_inc_release(cntO);
      if(tid==256&&blockIdx.x==0) STAMP(300+s);
    }
  } else {
    asm volatile("setmaxnreg.dec.sync.aligned.u32 40;");
    bar_sync(0,512);
    if(warp==12){
      { auto issue_x=[&](int s){ const uint32_t b=sb+HK_XA+(s&1)*HK_XSLOT, mb=mbXF+(s&1)*8; const size_t tb=((size_t)c*NSEG+s)*4096, qb=((size_t)c*NSEG+s)*1024;
          mbar_expect_tx(mb,(p.mode&64)? 0:HK_XSLOT);
          if(!(p.mode&64)){ bulk_g2s(b,g_qx+tb,8192,mb); bulk_g2s(b+8192,g_kx+tb,8192,mb); bulk_g2s(b+16384,g_vx+tb,8192,mb); bulk_g2s(b+24576,g_km+qb,2048,mb); bulk_g2s(b+26624,g_vm+qb,2048,mb); } };
        auto issue_o=[&](int s){ const uint32_t mb=mbOF+(s&1)*8;
          mbar_expect_tx(mb,(p.mode&32)? 0:32768);
          if(!(p.mode&32)) for(int j=0;j<8;j++) tma_2d(sb+HK_OT+(s&1)*32768+j*4096,&tmo,hg*512+j*64,s*32,mb);
          if(c==0) STAMP(600+s); };
        int sx=0, so=0, idle=0;
        while(sx<NSEG || so<NSEG){
          const int sg=(lane<2)? sx+lane : so+lane-2; const bool valid=(lane<4) && sg<NSEG;
          const unsigned* fp=(lane==4)? &g_ctrl.rpub : (lane<2)? &g_ctrl.segflag[min(sg,NSEG-1)*8] : &g_ctrl.oflag[min(sg,NSEG-1)*8+hg];
          unsigned v=0; if(lane<5) v=ld_acquire_u32(fp);
          bool ok=valid && (int)(v-((lane<2)? 96*E:4*E))>=0;
          if(ok && sg>=2) ok=mbar_test(((lane<2)? mbXE:mbOE)+(sg&1)*8,((sg>>1)-1)&1);
          const unsigned m=__ballot_sync(~0u,ok);
          const int nx=(m&1)? ((m&2)? 2:1):0, no=(m&4)? ((m&8)? 2:1):0;
          if(nx|no){
            const unsigned R=__shfl_sync(~0u,v,4); const int d=(int)(gtime32()-R);
            bool go=!(p.mode&256) || d>6000 || d<-6000 || (d>=(int)p.w0 && d<(int)p.w1);
            if(!go && d<(int)p.w0){ const unsigned T=R+p.w0; int k2=0; while((int)(gtime32()-T)<0 && ++k2<4000) __nanosleep(20); go=true; }
            if(go){
              if(lane==0){
                if(c==0 && no){ STAMP(400+so); STAMP(500+so); }
                asm volatile("fence.proxy.async.global;":::"memory");
                for(int i=0;i<nx;i++) issue_x(sx+i);
                for(int i=0;i<no;i++) issue_o(so+i); }
              sx+=nx; so+=no; idle=0; __syncwarp();
            } else __nanosleep(100);
          } else { __nanosleep(40); if(++idle>(1<<25)){ g_ctrl.err=25; break; } }
        } }
    } else if(warp==13 || warp==14){
      if(lane==0){ const uint32_t cnt=(warp==13)? cntO:cntP; const int per=(warp==13)? 4:8; unsigned* fl=(warp==13)? &g_ctrl.oflag[hg] : &g_ctrl.pcnt[cb];
        int done=0, idle=0;
        while(done<NSEG){
          const int n=(int)smem_ld_acquire(cnt)/per;
          if(n>done){ fence_gpu(); for(;done<n;done++) red_add_u32(fl+done*8,1); idle=0; }
          else { __nanosleep(20); if(++idle>(1<<26)){ g_ctrl.err=26; break; } } } }
    } else {
      auto ready=[&](int f){ unsigned v=0; if(lane<2) v=ld_acquire_u32(lane==0? &g_ctrl.pcnt[f*8+cb] : &g_ctrl.segflag[min(f+2,NSEG-1)*8]);
        const bool ok=(lane>=2) || ((int)(v-(lane==0? 8*E:96*E))>=0); return __all_sync(~0u,ok); };
      auto issue=[&](int f){ const uint32_t mb=mbFN+(f&1)*8;
        if(lane==0){ asm volatile("fence.proxy.async.global;":::"memory"); mbar_expect_tx(mb,(p.mode&16)? 0:16384); }
        if(lane==0 && !(p.mode&16)) bulk_g2s(sb+HK_FN+(f&1)*16384,g_pex+(size_t)(f&(PRING-1))*(8*SEG*DM)+(size_t)cb*32768+hg*4096,16384,mb);
        __syncwarp(); };
      auto wait_ready=[&](int f){ int c2=0; while(!ready(f)){ if(++c2>(1<<23)){ g_ctrl.err=24; break; } } };
      wait_ready(0); issue(0);
      for(int f=0;f<NSEG;f++){
        bool pre=false;
        if(f+1<NSEG && ready(f+1)){ issue(f+1); pre=true; }
        mbar_wait(mbFN+(f&1)*8,(f>>1)&1);
        if(lane==0&&c==0) STAMP(900+f);
        if(lane==0) red_add_u32(&g_ctrl.fcnt[f*8+cb],1);
        const uint32_t fb2=sb+HK_FN+(f&1)*16384+lane*16;
        #pragma unroll
        for(int i=0;i<4;i++){
          float4 a=lds128f(fb2+i*512);
          #pragma unroll
          for(int k2=1;k2<8;k2++){ const float4 v=lds128f(fb2+(k2*4+i)*512); a.x+=v.x; a.y+=v.y; a.z+=v.z; a.w+=v.w; }
          *(uint2*)(p.out+(size_t)(f*32+4*hg+i)*1024+512+cb*128+lane*4)=make_uint2(pack_bf16(a.x,a.y),pack_bf16(a.z,a.w)); }
        __syncwarp();
        if(f+1<NSEG && !pre){ wait_ready(f+1); issue(f+1); }
      }
      if(lane==0&&blockIdx.x==31) STAMP(5);
      if(lane==0&&blockIdx.x==0) STAMP(6);
    }
  }
  __syncwarp();
  if(warp==15) asm volatile("griddepcontrol.wait;":::"memory");
}
}

typedef CUresult (*EncFn)(CUtensorMap*,CUtensorMapDataType,cuuint32_t,void*,const cuuint64_t*,const cuuint64_t*,const cuuint32_t*,const cuuint32_t*,CUtensorMapInterleave,CUtensorMapSwizzle,CUtensorMapL2promotion,CUtensorMapFloatOOBfill);

extern "C" void kernel_launch(void* const* d_in, const int* in_sizes, int n_in, void* d_out, int out_size){
  const bf16* x=(const bf16*)d_in[9];
  cudaStream_t st=cudaStreamPerThread;
  static CUtensorMap tmx, tmo, tmw[3], tmwo; static const void* tm_x=nullptr;
  if(tm_x!=(const void*)x){
    cudaFuncSetAttribute(chain_kernel,cudaFuncAttributeMaxDynamicSharedMemorySize,SM_TOTAL+1024);
    cudaFuncSetAttribute(helper_kernel,cudaFuncAttributeMaxDynamicSharedMemorySize,HK_TOTAL);
    void* fn=nullptr; cudaDriverEntryPointQueryResult qr; cudaGetDriverEntryPoint("cuTensorMapEncodeTiled",&fn,cudaEnableDefault,&qr);
    { cuuint64_t gd[2]={512,2048}, gs[1]={1024}; cuuint32_t bx[2]={64,32}, es[2]={1,1};
      ((EncFn)fn)(&tmx,CU_TENSOR_MAP_DATA_TYPE_BFLOAT16,2,(void*)x,gd,gs,bx,es,CU_TENSOR_MAP_INTERLEAVE_NONE,CU_TENSOR_MAP_SWIZZLE_128B,CU_TENSOR_MAP_L2_PROMOTION_L2_128B,CU_TENSOR_MAP_FLOAT_OOB_FILL_NONE); }
    { void* po=nullptr; cudaGetSymbolAddress(&po,g_o);
      cuuint64_t gd[2]={4096,2048}, gs[1]={8192}; cuuint32_t bx[2]={64,32}, es[2]={1,1};
      ((EncFn)fn)(&tmo,CU_TENSOR_MAP_DATA_TYPE_BFLOAT16,2,po,gd,gs,bx,es,CU_TENSOR_MAP_INTERLEAVE_NONE,CU_TENSOR_MAP_SWIZZLE_128B,CU_TENSOR_MAP_L2_PROMOTION_L2_128B,CU_TENSOR_MAP_FLOAT_OOB_FILL_NONE); }
    for(int i=0;i<3;i++){ cuuint64_t gd[2]={4096,512}, gs[1]={8192}; cuuint32_t bx[2]={64,256}, es[2]={1,1};
      ((EncFn)fn)(&tmw[i],CU_TENSOR_MAP_DATA_TYPE_BFLOAT16,2,d_in[11+i],gd,gs,bx,es,CU_TENSOR_MAP_INTERLEAVE_NONE,CU_TENSOR_MAP_SWIZZLE_128B,CU_TENSOR_MAP_L2_PROMOTION_L2_256B,CU_TENSOR_MAP_FLOAT_OOB_FILL_NONE); }
    { cuuint64_t gd[2]={512,4096}, gs[1]={1024}; cuuint32_t bx[2]={64,128}, es[2]={1,1};
      ((EncFn)fn)(&tmwo,CU_TENSOR_MAP_DATA_TYPE_BFLOAT16,2,d_in[14],gd,gs,bx,es,CU_TENSOR_MAP_INTERLEAVE_NONE,CU_TENSOR_MAP_SWIZZLE_128B,CU_TENSOR_MAP_L2_PROMOTION_L2_256B,CU_TENSOR_MAP_FLOAT_OOB_FILL_NONE); }
    tm_x=(const void*)x; }
  ChainP p; p.x=x; p.mem0=(const bf16*)d_in[10]; p.Wo=(const bf16*)d_in[14];
  p.delay=1000; p.d0=608; p.lam0=2300; p.fpen=450; p.boff=150;
  { cudaLaunchConfig_t cfg={}; cfg.gridDim=dim3(96); cfg.blockDim=dim3(384); cfg.dynamicSmemBytes=SM_TOTAL+1024; cfg.stream=st;
    cudaLaunchAttribute at[1]; at[0].id=cudaLaunchAttributeClusterDimension; at[0].val.clusterDim.x=3; at[0].val.clusterDim.y=1; at[0].val.clusterDim.z=1; cfg.attrs=at; cfg.numAttrs=1;
    cudaLaunchKernelEx(&cfg,chain_kernel,p,tmx,tmw[0],tmw[1],tmw[2],tmwo); }
  HelpP hp; hp.u=(const bf16*)d_in[0]; hp.Are=(const bf16*)d_in[1]; hp.Aim=(const bf16*)d_in[2]; hp.Bre=(const bf16*)d_in[3]; hp.Bim=(const bf16*)d_in[4];
  hp.Cre=(const bf16*)d_in[5]; hp.Cim=(const bf16*)d_in[6]; hp.logdt=(const bf16*)d_in[7]; hp.Dsk=(const bf16*)d_in[8]; hp.Wo=(const bf16*)d_in[14]; hp.out=(bf16*)d_out; hp.mode=0; hp.w0=650; hp.w1=1300;
  { cudaLaunchConfig_t cfg={}; cfg.gridDim=dim3(32); cfg.blockDim=dim3(512); cfg.dynamicSmemBytes=HK_TOTAL; cfg.stream=st;
    cudaLaunchAttribute at[1]; at[0].id=cudaLaunchAttributeProgrammaticStreamSerialization; at[0].val.programmaticStreamSerializationAllowed=1; cfg.attrs=at; cfg.numAttrs=1;
    cudaLaunchKernelEx(&cfg,helper_kernel,hp,tmo); }
}
```
